```python
import torch

def _softmax(x, axis=-1):
    return torch.softmax(x, dim=axis)

def _gelu(x):
    return torch.nn.functional.gelu(x, approximate='tanh')

def _silu(x):
    return torch.nn.functional.silu(x)

def _sigmoid(x):
    return torch.sigmoid(x)

def _layernorm(x, axis=-1, eps=1e-05):
    m = x.mean(dim=axis, keepdim=True)
    v = x.var(dim=axis, keepdim=True, unbiased=False)
    return (x - m) / torch.sqrt(v + eps)

def _scatter_add(tgt, idx, src, axis=0):
    return tgt.clone().index_add_(axis, idx, src)

def _segment_sum(src, seg, n):
    out = torch.zeros((n,) + src.shape[1:], dtype=src.dtype)
    return out.index_add_(0, seg, src)

def _pad(x, pw):
    flat = tuple((v for pair in reversed(pw) for v in pair))
    return torch.nn.functional.pad(x, flat)
kernel_name = 'standalone__tree_speculative_verify_tree_attention_over_candidate_token_tree__decode'

def setup_inputs():

    _w = lambda a: (lambda t: t.to(torch.bfloat16) if t.is_floating_point() else t)(torch.as_tensor(a))
    B, Hq, Hkv, T, C, D = (2, 32, 16, 1, 4096, 128)
    tree_mask = torch.zeros((B, T, T), dtype=float)
    for b in range(B):
        parent = torch.zeros(T, dtype=torch.int64)
        for i in range(1, T):
            parent[i] = int(torch.randint(0, i, (1,)).item())
        for i in range(T):
            j = i
            tree_mask[b, i, j] = 1.0
            while j > 0:
                j = parent[j]
                tree_mask[b, i, j] = 1.0
    return {'q': _w((lambda *s: torch.randn(*s, dtype=torch.bfloat16) * 0.8)(B, Hq, T, D)), 'k_cache': _w((lambda *s: torch.randn(*s, dtype=torch.bfloat16) * 0.8)(B, Hkv, C, D)), 'v_cache': _w((lambda *s: torch.randn(*s, dtype=torch.bfloat16) * 0.05)(B, Hkv, C, D)), 'k_tree': _w((lambda *s: torch.randn(*s, dtype=torch.bfloat16) * 0.8)(B, Hkv, T, D)), 'v_tree': _w((lambda *s: torch.randn(*s, dtype=torch.bfloat16) * 0.05)(B, Hkv, T, D)), 'tree_mask': _w(tree_mask)}

def reference(q, k_cache, v_cache, k_tree, v_tree, tree_mask):
    B, Hq, T, D = q.shape
    Hkv, C = (k_cache.shape[1], k_cache.shape[2])
    rep = Hq // Hkv
    kc = (lambda x, n, axis: torch.repeat_interleave(x, n, dim=axis))(k_cache, rep, axis=1)
    vc = (lambda x, n, axis: torch.repeat_interleave(x, n, dim=axis))(v_cache, rep, axis=1)
    kt = (lambda x, n, axis: torch.repeat_interleave(x, n, dim=axis))(k_tree, rep, axis=1)
    vt = (lambda x, n, axis: torch.repeat_interleave(x, n, dim=axis))(v_tree, rep, axis=1)
    k = torch.concatenate([kc, kt], axis=2)
    v = torch.concatenate([vc, vt], axis=2)
    scale = D ** (-0.5)
    scores = torch.einsum('bhqd,bhkd->bhqk', q, k) * scale
    ctx_mask = torch.ones((B, 1, T, C), dtype=scores.dtype)
    tm = tree_mask[:, None, :, :].clone()
    full_mask = torch.concatenate([ctx_mask, tm], axis=-1)
    scores = scores + (1.0 - full_mask) * -1000000000.0
    p = _softmax(scores, axis=-1)
    return torch.einsum('bhqk,bhkd->bhqd', p, v)
```

```cpp
#include <cuda_runtime.h>
#include <cuda_bf16.h>
#include <cuda.h>
#include <cudaTypedefs.h>
#include <stdint.h>

namespace {

constexpr int kD = 128;
constexpr int kC = 4096;
constexpr int kHkv = 16;
constexpr int kB = 2;
constexpr int kCluster = 4;
constexpr int kTile = 64;
constexpr int kNT = kC / kTile / kCluster;
#define STAGES 4
constexpr int kStages = STAGES;
constexpr int kStageBytes = kTile * kD * 2;
constexpr int kConsumerWarps = 8;
constexpr int kThreads = (kConsumerWarps + 1) * 32;

constexpr int kOffS = kStages * kStageBytes;
constexpr int kSPitch = 1024 + 4;
constexpr int kOffP = kOffS + 2 * kSPitch * 4;
constexpr int kPPitch = (1024 + 8) * 2;
constexpr int kOffPart = kOffP + 2 * kPPitch;
constexpr int kOffWmax = kOffPart + 4 * 8 * 32 * 4;
constexpr int kOffStatM = kOffWmax + 64;
constexpr int kOffStatL = kOffStatM + 32;
constexpr int kOffTree = kOffStatL + 128;
constexpr int kOffBar = kOffTree + 16;
constexpr int kSmemBytes = kOffBar + (2 * kStages + 2) * 8;
static_assert(kOffP % 16 == 0 && kOffPart % 16 == 0 && kOffWmax % 16 == 0 && kOffStatL % 16 == 0 && kOffBar % 8 == 0, "align");

constexpr float kLog2e = 1.4426950408889634f;
constexpr float kScale = 0.08838834764831845f;
constexpr float kScaleLog2e = kScale * kLog2e;

#define TSTAMP(i)
#define TSTAMP_P(i)

__device__ __forceinline__ void mbar_init(uint32_t bar, uint32_t cnt) {
    asm volatile("mbarrier.init.shared::cta.b64 [%0], %1;" :: "r"(bar), "r"(cnt) : "memory");
}
__device__ __forceinline__ void mbar_expect_tx(uint32_t bar, uint32_t bytes) {
    asm volatile("mbarrier.arrive.expect_tx.shared::cta.b64 _, [%0], %1;" :: "r"(bar), "r"(bytes) : "memory");
}
__device__ __forceinline__ void mbar_arrive(uint32_t bar) {
    asm volatile("mbarrier.arrive.shared::cta.b64 _, [%0];" :: "r"(bar) : "memory");
}
__device__ __forceinline__ bool mbar_try(uint32_t bar, uint32_t parity) {
    uint32_t ok;
    asm volatile("{\n.reg .pred p;\nmbarrier.try_wait.parity.shared::cta.b64 p, [%1], %2;\nselp.u32 %0, 1, 0, p;\n}"
                 : "=r"(ok) : "r"(bar), "r"(parity) : "memory");
    return ok;
}
__device__ __forceinline__ bool mbar_try_cluster(uint32_t bar, uint32_t parity) {
    uint32_t ok;
    asm volatile("{\n.reg .pred p;\nmbarrier.try_wait.parity.acquire.cluster.shared::cta.b64 p, [%1], %2;\nselp.u32 %0, 1, 0, p;\n}"
                 : "=r"(ok) : "r"(bar), "r"(parity) : "memory");
    return ok;
}
__device__ __forceinline__ void mbar_wait(uint32_t bar, uint32_t parity) {
    if (mbar_try(bar, parity)) return;
    uint32_t n = 0;
    while (!mbar_try(bar, parity)) { if (++n > (1u << 22)) __trap(); }
}
__device__ __forceinline__ void mbar_wait_cluster(uint32_t bar, uint32_t parity) {
    if (mbar_try_cluster(bar, parity)) return;
    uint32_t n = 0;
    while (!mbar_try_cluster(bar, parity)) { if (++n > (1u << 22)) __trap(); }
}
__device__ __forceinline__ void tma_tile(uint32_t dst, const CUtensorMap* tm, uint32_t bar, int row) {
    asm volatile("cp.async.bulk.tensor.3d.shared::cluster.global.mbarrier::complete_tx::bytes [%0], [%1, {%3, %4, %5}], [%2];"
                 :: "r"(dst), "l"(tm), "r"(bar), "r"(0), "r"(row), "r"(0) : "memory");
}
__device__ __forceinline__ void ldsm4(uint32_t addr, uint32_t& r0, uint32_t& r1, uint32_t& r2, uint32_t& r3) {
    asm volatile("ldmatrix.sync.aligned.m8n8.x4.shared.b16 {%0,%1,%2,%3}, [%4];"
                 : "=r"(r0), "=r"(r1), "=r"(r2), "=r"(r3) : "r"(addr) : "memory");
}
__device__ __forceinline__ void ldsm4t(uint32_t addr, uint32_t& r0, uint32_t& r1, uint32_t& r2, uint32_t& r3) {
    asm volatile("ldmatrix.sync.aligned.m8n8.x4.trans.shared.b16 {%0,%1,%2,%3}, [%4];"
                 : "=r"(r0), "=r"(r1), "=r"(r2), "=r"(r3) : "r"(addr) : "memory");
}
__device__ __forceinline__ void mma16816(float (&c)[4], uint32_t a0, uint32_t a1, uint32_t a2, uint32_t a3, uint32_t b0, uint32_t b1) {
    asm volatile("mma.sync.aligned.m16n8k16.row.col.f32.bf16.bf16.f32 {%0,%1,%2,%3}, {%4,%5,%6,%7}, {%8,%9}, {%0,%1,%2,%3};"
                 : "+f"(c[0]), "+f"(c[1]), "+f"(c[2]), "+f"(c[3])
                 : "r"(a0), "r"(a1), "r"(a2), "r"(a3), "r"(b0), "r"(b1));
}
__device__ __forceinline__ uint32_t mapa(uint32_t addr, uint32_t rank) {
    uint32_t r;
    asm("mapa.shared::cluster.u32 %0, %1, %2;" : "=r"(r) : "r"(addr), "r"(rank));
    return r;
}
__device__ __forceinline__ void st_async_v4(uint32_t addr, float a, float b, float c, float d, uint32_t bar) {
    asm volatile("st.async.weak.shared::cluster.mbarrier::complete_tx::bytes.v4.f32 [%0], {%1,%2,%3,%4}, [%5];"
                 :: "r"(addr), "f"(a), "f"(b), "f"(c), "f"(d), "r"(bar) : "memory");
}
__device__ __forceinline__ void st_async_f32(uint32_t addr, float a, uint32_t bar) {
    asm volatile("st.async.weak.shared::cluster.mbarrier::complete_tx::bytes.f32 [%0], %1, [%2];"
                 :: "r"(addr), "f"(a), "r"(bar) : "memory");
}
__device__ __forceinline__ float ex2(float x) { float y; asm("ex2.approx.ftz.f32 %0, %1;" : "=f"(y) : "f"(x)); return y; }
__device__ __forceinline__ uint32_t pack_bf16(float lo, float hi) {
    uint32_t r;
    asm("cvt.rn.bf16x2.f32 %0, %1, %2;" : "=r"(r) : "f"(hi), "f"(lo));
    return r;
}
__device__ __forceinline__ float bf_lo(uint32_t v) { return __uint_as_float(v << 16); }
__device__ __forceinline__ float bf_hi(uint32_t v) { return __uint_as_float(v & 0xffff0000u); }
__device__ __forceinline__ void bar_consumers() { asm volatile("bar.sync 1, 256;" ::: "memory"); }

__global__ void __cluster_dims__(kCluster, 1, 1) __launch_bounds__(kThreads, 2)
tree_attn_kernel(const __grid_constant__ CUtensorMap tmK, const __grid_constant__ CUtensorMap tmV,
                 const __nv_bfloat16* __restrict__ q, const __nv_bfloat16* __restrict__ k_tree,
                 const __nv_bfloat16* __restrict__ v_tree, const __nv_bfloat16* __restrict__ mask,
                 __nv_bfloat16* __restrict__ out)
{
    extern __shared__ __align__(1024) unsigned char smem[];
    const uint32_t sb = (uint32_t)__cvta_generic_to_shared(smem);
    const int warp = threadIdx.x >> 5;
    const int lane = threadIdx.x & 31;
    const uint32_t rank = blockIdx.x & (kCluster - 1);
    const int hp = blockIdx.x / kCluster;
    const uint32_t barFull = sb + kOffBar;
    const uint32_t barEmpty = barFull + kStages * 8;
    const uint32_t barStat = barEmpty + kStages * 8;
    const uint32_t barFin = barStat + 8;

    if (warp == kConsumerWarps) {
        const int row0 = hp * kC + (int)rank * kTile;
        if (lane == 0) {
            TSTAMP_P(0);
#pragma unroll
            for (int s = 0; s < kStages; s++) {
                mbar_init(barFull + s * 8, 1);
                mbar_expect_tx(barFull + s * 8, kStageBytes);
                tma_tile(sb + s * kStageBytes, &tmK, barFull + s * 8, row0 + s * (kCluster * kTile));
            }
            TSTAMP_P(1);
#pragma unroll
            for (int s = 0; s < kStages; s++) mbar_init(barEmpty + s * 8, kConsumerWarps);
            mbar_init(barStat, 1);
            mbar_init(barFin, 1);
            mbar_expect_tx(barStat, kCluster * (8 + 2) * 4);
            mbar_expect_tx(barFin, kCluster * 8 * 8 * 16);
            asm volatile("fence.mbarrier_init.release.cluster;" ::: "memory");
        }
        __syncthreads();
        asm volatile("barrier.cluster.arrive.relaxed.aligned;" ::: "memory");
        if (lane == 0) {
            int s = 0; uint32_t ph = 0;
            for (int j = kStages; j < 2 * kNT; j++) {
                mbar_wait(barEmpty + s * 8, ph);
                mbar_expect_tx(barFull + s * 8, kStageBytes);
                const bool isK = j < kNT;
                tma_tile(sb + s * kStageBytes, isK ? &tmK : &tmV, barFull + s * 8, row0 + (isK ? j : j - kNT) * (kCluster * kTile));
                if (++s == kStages) { s = 0; ph ^= 1; }
            }
            TSTAMP_P(2);
        }
        __syncwarp();
        asm volatile("barrier.cluster.wait.aligned;" ::: "memory");
        return;
    }

    const int g = lane >> 2, t = lane & 3;
    TSTAMP(3);
    uint32_t qa[8][2];
    {
        const uint32_t* qp = reinterpret_cast<const uint32_t*>(q + (size_t)(hp * 2 + (g & 1)) * kD) + t;
#pragma unroll
        for (int ks = 0; ks < 8; ks++) { qa[ks][0] = __ldg(qp + ks * 8); qa[ks][1] = __ldg(qp + ks * 8 + 4); }
    }
    const int odim = warp * 16 + g + ((t >> 1) << 3);
    float vtree = 0.f;
    if (rank == 0) {
        vtree = __bfloat162float(v_tree[hp * kD + odim]);
        if (warp == 0) {
            const uint2 kt = __ldg(reinterpret_cast<const uint2*>(k_tree + hp * kD) + lane);
            const uint2 q0 = __ldg(reinterpret_cast<const uint2*>(q + (size_t)(hp * 2) * kD) + lane);
            const uint2 q1 = __ldg(reinterpret_cast<const uint2*>(q + (size_t)(hp * 2 + 1) * kD) + lane);
            const float mk = __bfloat162float(mask[hp / kHkv]);
            float d0 = bf_lo(kt.x) * bf_lo(q0.x) + bf_hi(kt.x) * bf_hi(q0.x) + bf_lo(kt.y) * bf_lo(q0.y) + bf_hi(kt.y) * bf_hi(q0.y);
            float d1 = bf_lo(kt.x) * bf_lo(q1.x) + bf_hi(kt.x) * bf_hi(q1.x) + bf_lo(kt.y) * bf_lo(q1.y) + bf_hi(kt.y) * bf_hi(q1.y);
#pragma unroll
            for (int o = 16; o > 0; o >>= 1) { d0 += __shfl_xor_sync(~0u, d0, o); d1 += __shfl_xor_sync(~0u, d1, o); }
            const float madd = (1.0f - mk) * -1000000000.0f;
            if (lane < 2) reinterpret_cast<float*>(smem + kOffTree)[lane] = ((lane ? d1 : d0) * kScale + madd) * kLog2e;
        }
    }
    __syncthreads();
    asm volatile("barrier.cluster.arrive.relaxed.aligned;" ::: "memory");

    int s = 0; uint32_t ph = 0;
    {
        const uint32_t koff = (uint32_t)(warp * 8 + (lane & 7)) * 128 + ((((lane >> 3) ^ (lane & 7))) << 4);
        float* Sp = reinterpret_cast<float*>(smem + kOffS) + (g & 1) * kSPitch + t * 16 + warp * 2;
        float mx = -INFINITY;
        for (int j = 0; j < kNT; j++) {
            mbar_wait(barFull + s * 8, ph);
            if (j == 0) TSTAMP(4);
            const uint32_t base = sb + s * kStageBytes;
            uint32_t kf[4][4];
            ldsm4(base + koff, kf[0][0], kf[0][1], kf[0][2], kf[0][3]);
            ldsm4(base + (koff ^ 64), kf[1][0], kf[1][1], kf[1][2], kf[1][3]);
            ldsm4(base + koff + 8192, kf[2][0], kf[2][1], kf[2][2], kf[2][3]);
            ldsm4(base + (koff ^ 64) + 8192, kf[3][0], kf[3][1], kf[3][2], kf[3][3]);
            __syncwarp();
            if (lane == 0) mbar_arrive(barEmpty + s * 8);
            float c0[4] = {0.f, 0.f, 0.f, 0.f}, c1[4] = {0.f, 0.f, 0.f, 0.f};
#pragma unroll
            for (int i = 0; i < 4; i++) {
                mma16816(c0, qa[2 * i][0], 0u, qa[2 * i][1], 0u, kf[i][0], kf[i][1]);
                mma16816(c1, qa[2 * i + 1][0], 0u, qa[2 * i + 1][1], 0u, kf[i][2], kf[i][3]);
            }
            const float s0 = c0[0] + c1[0], s1 = c0[1] + c1[1];
            mx = fmaxf(mx, fmaxf(s0, s1));
            if (g < 2) *reinterpret_cast<float2*>(Sp + j * 64) = make_float2(s0, s1);
            if (++s == kStages) { s = 0; ph ^= 1; }
        }
        mx = fmaxf(mx, __shfl_xor_sync(~0u, mx, 1));
        mx = fmaxf(mx, __shfl_xor_sync(~0u, mx, 2));
        if (t == 0 && g < 2) reinterpret_cast<float*>(smem + kOffWmax)[g * 8 + warp] = mx;
    }
    TSTAMP(5);
    bar_consumers();

    asm volatile("barrier.cluster.wait.aligned;" ::: "memory");
    {
        const int h = warp >> 2;
        const int idx = threadIdx.x & 127;
        const float4 m0 = *reinterpret_cast<const float4*>(smem + kOffWmax + h * 32);
        const float4 m1 = *reinterpret_cast<const float4*>(smem + kOffWmax + h * 32 + 16);
        const float4 a = *reinterpret_cast<const float4*>(smem + kOffS + h * (kSPitch * 4) + idx * 32);
        const float4 b = *reinterpret_cast<const float4*>(smem + kOffS + h * (kSPitch * 4) + idx * 32 + 16);
        const float m = fmaxf(fmaxf(fmaxf(m0.x, m0.y), fmaxf(m0.z, m0.w)), fmaxf(fmaxf(m1.x, m1.y), fmaxf(m1.z, m1.w))) * kScaleLog2e;
        const float p0 = ex2(fmaf(a.x, kScaleLog2e, -m)), p1 = ex2(fmaf(a.y, kScaleLog2e, -m));
        const float p2 = ex2(fmaf(a.z, kScaleLog2e, -m)), p3 = ex2(fmaf(a.w, kScaleLog2e, -m));
        const float p4 = ex2(fmaf(b.x, kScaleLog2e, -m)), p5 = ex2(fmaf(b.y, kScaleLog2e, -m));
        const float p6 = ex2(fmaf(b.z, kScaleLog2e, -m)), p7 = ex2(fmaf(b.w, kScaleLog2e, -m));
        uint4 pk;
        pk.x = pack_bf16(p0, p1); pk.y = pack_bf16(p2, p3); pk.z = pack_bf16(p4, p5); pk.w = pack_bf16(p6, p7);
        *reinterpret_cast<uint4*>(smem + kOffP + h * kPPitch + idx * 16) = pk;
        bar_consumers();
        float sum = ((p0 + p1) + (p2 + p3)) + ((p4 + p5) + (p6 + p7));
#pragma unroll
        for (int o = 16; o > 0; o >>= 1) sum += __shfl_xor_sync(~0u, sum, o);
        if (lane == 0) {
            const uint32_t rbar = mapa(barStat, 0);
            st_async_f32(mapa(sb + kOffStatL + (rank * 8 + warp) * 4, 0), sum, rbar);
            if ((warp & 3) == 0) st_async_f32(mapa(sb + kOffStatM + (rank * 2 + h) * 4, 0), m, rbar);
        }
    }
    TSTAMP(6);

    float o0[4] = {0.f, 0.f, 0.f, 0.f}, o1[4] = {0.f, 0.f, 0.f, 0.f};
    float f0 = 0.f, f1 = 0.f, f2 = 0.f, f3 = 0.f, ft = 0.f;
    {
        const int mi = lane >> 3;
        const uint32_t voff = (uint32_t)(warp >> 2) * 8192 + (uint32_t)((mi >> 1) * 8 + (lane & 7)) * 128
                            + (((((warp * 2) & 7) + (mi & 1)) ^ (lane & 7)) << 4);
        const unsigned char* Pp = smem + kOffP + (g & 1) * kPPitch + t * 32;
        for (int j = 0; j < kNT; j++) {
            const uint4 pa = *reinterpret_cast<const uint4*>(Pp + j * 128);
            const uint4 pb = *reinterpret_cast<const uint4*>(Pp + j * 128 + 16);
            if (j == kNT - 3 && rank == 0) {
                mbar_wait_cluster(barStat, 0);
                const int h = t & 1;
                const float* sm = reinterpret_cast<const float*>(smem + kOffStatM);
                const float m0 = sm[h], m1 = sm[2 + h], m2 = sm[4 + h], m3 = sm[6 + h];
                const float xt = reinterpret_cast<const float*>(smem + kOffTree)[h];
                const float M = fmaxf(fmaxf(fmaxf(m0, m1), fmaxf(m2, m3)), xt);
                const float4* sl = reinterpret_cast<const float4*>(smem + kOffStatL) + h;
                const float4 l0 = sl[0], l1 = sl[2], l2 = sl[4], l3 = sl[6];
                f0 = ex2(m0 - M); f1 = ex2(m1 - M); f2 = ex2(m2 - M); f3 = ex2(m3 - M); ft = ex2(xt - M);
                const float L = f0 * ((l0.x + l0.y) + (l0.z + l0.w)) + f1 * ((l1.x + l1.y) + (l1.z + l1.w))
                              + f2 * ((l2.x + l2.y) + (l2.z + l2.w)) + f3 * ((l3.x + l3.y) + (l3.z + l3.w)) + ft;
                const float inv = 1.0f / L;
                f0 *= inv; f1 *= inv; f2 *= inv; f3 *= inv; ft *= inv;
            }
            mbar_wait(barFull + s * 8, ph);
            const uint32_t base = sb + s * kStageBytes + voff;
            uint32_t vf[4][4];
#pragma unroll
            for (int ks = 0; ks < 4; ks++) ldsm4t(base + ks * 2048, vf[ks][0], vf[ks][1], vf[ks][2], vf[ks][3]);
            __syncwarp();
            if (lane == 0) mbar_arrive(barEmpty + s * 8);
            mma16816(o0, vf[0][0], vf[0][1], vf[0][2], vf[0][3], pa.x, pa.y);
            mma16816(o1, vf[1][0], vf[1][1], vf[1][2], vf[1][3], pa.z, pa.w);
            mma16816(o0, vf[2][0], vf[2][1], vf[2][2], vf[2][3], pb.x, pb.y);
            mma16816(o1, vf[3][0], vf[3][1], vf[3][2], vf[3][3], pb.z, pb.w);
            if (++s == kStages) { s = 0; ph ^= 1; }
        }
    }
    TSTAMP(7);
    if (t == 0)
        st_async_v4(mapa(sb + kOffPart + ((rank * 8 + warp) * 32 + lane) * 4, 0),
                    o0[0] + o1[0], o0[1] + o1[1], o0[2] + o1[2], o0[3] + o1[3], mapa(barFin, 0));
    if (rank == 0) {
        mbar_wait_cluster(barFin, 0);
        TSTAMP(8);
        const float* pp = reinterpret_cast<const float*>(smem + kOffPart) + warp * 32 + lane;
        const float r = f0 * pp[0] + f1 * pp[256] + f2 * pp[512] + f3 * pp[768] + ft * vtree;
        out[(size_t)(hp * 2 + (t & 1)) * kD + odim] = __float2bfloat16(r);
    }
    TSTAMP(9);
}

}

extern "C" void kernel_launch(void* const* d_in, const int* in_sizes, int n_in, void* d_out, int out_size) {
    const __nv_bfloat16* q  = (const __nv_bfloat16*)d_in[0];
    const __nv_bfloat16* kc = (const __nv_bfloat16*)d_in[1];
    const __nv_bfloat16* vc = (const __nv_bfloat16*)d_in[2];
    const __nv_bfloat16* kt = (const __nv_bfloat16*)d_in[3];
    const __nv_bfloat16* vt = (const __nv_bfloat16*)d_in[4];
    const __nv_bfloat16* mk = (const __nv_bfloat16*)d_in[5];
    static PFN_cuTensorMapEncodeTiled_v12000 enc = nullptr;
    if (!enc) {
        cudaDriverEntryPointQueryResult qr;
        cudaGetDriverEntryPoint("cuTensorMapEncodeTiled", (void**)&enc, cudaEnableDefault, &qr);
        cudaFuncSetAttribute(tree_attn_kernel, cudaFuncAttributeMaxDynamicSharedMemorySize, kSmemBytes);
    }
    CUtensorMap tmK, tmV;
    cuuint64_t dims[3] = {64, (cuuint64_t)kB * kHkv * kC, 2};
    cuuint64_t strides[2] = {256, 128};
    cuuint32_t box[3] = {64, (cuuint32_t)kTile, 2};
    cuuint32_t es[3] = {1, 1, 1};
    enc(&tmK, CU_TENSOR_MAP_DATA_TYPE_BFLOAT16, 3, (void*)kc, dims, strides, box, es, CU_TENSOR_MAP_INTERLEAVE_NONE,
        CU_TENSOR_MAP_SWIZZLE_128B, CU_TENSOR_MAP_L2_PROMOTION_NONE, CU_TENSOR_MAP_FLOAT_OOB_FILL_NONE);
    enc(&tmV, CU_TENSOR_MAP_DATA_TYPE_BFLOAT16, 3, (void*)vc, dims, strides, box, es, CU_TENSOR_MAP_INTERLEAVE_NONE,
        CU_TENSOR_MAP_SWIZZLE_128B, CU_TENSOR_MAP_L2_PROMOTION_NONE, CU_TENSOR_MAP_FLOAT_OOB_FILL_NONE);
    tree_attn_kernel<<<kB * kHkv * kCluster, kThreads, kSmemBytes, cudaStreamPerThread>>>(tmK, tmV, q, kt, vt, mk, (__nv_bfloat16*)d_out);
}
```

```cpp
#include <cuda_runtime.h>
#include <cuda_bf16.h>
#include <cuda.h>
#include <cudaTypedefs.h>
#include <stdint.h>

namespace {

constexpr int kD = 128;
constexpr int kC = 4096;
constexpr int kHkv = 16;
constexpr int kB = 2;
constexpr int kGroup = 4;
constexpr int kTile = 64;
constexpr int kNT = kC / kTile / kGroup;
constexpr int kStages = 6;
constexpr int kDepth = 5;
constexpr int kInit = 2;
constexpr int kStageBytes = kTile * kD * 2;
constexpr int kConsumerWarps = 8;
constexpr int kAuxWarps = 4;
constexpr int kThreads = (kConsumerWarps + kAuxWarps) * 32;
constexpr int kLag = 4;
constexpr int kChunks = 4;
constexpr int kFoldStep = 13;

constexpr int kOffS = kStages * kStageBytes;
constexpr int kSPitch = 1024 + 4;
constexpr int kOffP = kOffS + 2 * kSPitch * 4;
constexpr int kPPitch = (1024 + 8) * 2;
constexpr int kPRank = 2 * kPPitch;
constexpr int kOffF = kOffP + kGroup * kPRank;
constexpr int kOffBar = kOffF + 160;
constexpr int kSmemBytes = kOffBar + (kThreads / 32) * 256;
static_assert(kOffP % 16 == 0 && kOffF % 16 == 0 && kOffBar % 8 == 0, "align");

__device__ uint4 g_P[128][kChunks * 2][32];
__device__ ulonglong2 g_stat[128][kChunks * 2];
__device__ uint32_t g_epoch[128];

constexpr float kLog2e = 1.4426950408889634f;
constexpr float kScale = 0.08838834764831845f;
constexpr float kScaleLog2e = kScale * kLog2e;


__device__ __forceinline__ void mbar_init(uint32_t bar, uint32_t cnt) {
    asm volatile("mbarrier.init.shared::cta.b64 [%0], %1;" :: "r"(bar), "r"(cnt) : "memory");
}
__device__ __forceinline__ void mbar_expect_tx(uint32_t bar, uint32_t bytes) {
    asm volatile("mbarrier.arrive.expect_tx.shared::cta.b64 _, [%0], %1;" :: "r"(bar), "r"(bytes) : "memory");
}
__device__ __forceinline__ void mbar_arrive(uint32_t bar) {
    asm volatile("mbarrier.arrive.shared::cta.b64 _, [%0];" :: "r"(bar) : "memory");
}
__device__ __forceinline__ void mbar_wait(uint32_t bar, uint32_t parity) {
    asm volatile("{\n.reg .pred p;\n.reg .u32 n;\nmov.u32 n, 0;\n"
                 "WAIT:\nmbarrier.try_wait.parity.shared::cta.b64 p, [%0], %1;\n@p bra DONE;\n"
                 "add.u32 n, n, 1;\nsetp.lt.u32 p, n, 0x400000;\n@p bra WAIT;\ntrap;\nDONE:\n}"
                 :: "r"(bar), "r"(parity) : "memory");
}
__device__ __forceinline__ void mbar_arrive2(uint32_t bar) {
    asm volatile("mbarrier.arrive.shared::cta.b64 _, [%0], 2;" :: "r"(bar) : "memory");
}
__device__ __forceinline__ bool elect_one() {
    uint32_t pred;
    asm volatile("{\n.reg .pred p;\nelect.sync _|p, 0xffffffff;\nselp.u32 %0, 1, 0, p;\n}" : "=r"(pred) :: "memory");
    return pred;
}
__device__ __forceinline__ uint32_t gtime32() { uint32_t t; asm volatile("mov.u32 %0, %globaltimer_lo;" : "=r"(t) :: "memory"); return t; }
constexpr unsigned long long kEvictFirst = 0x12F0000000000000ull;
__device__ __forceinline__ void bulk_k(uint32_t dst, const void* src, uint32_t bar) {
    asm volatile("cp.async.bulk.shared::cluster.global.mbarrier::complete_tx::bytes.L2::cache_hint [%0], [%1], %3, [%2], %4;"
                 :: "r"(dst), "l"(src), "r"(bar), "n"(kStageBytes), "l"(kEvictFirst) : "memory");
}
__device__ __forceinline__ uint4 lds128(uint32_t addr) {
    uint4 v; asm volatile("ld.shared.v4.u32 {%0,%1,%2,%3}, [%4];" : "=r"(v.x), "=r"(v.y), "=r"(v.z), "=r"(v.w) : "r"(addr) : "memory"); return v;
}
__device__ __forceinline__ void ldsm4t(uint32_t addr, uint32_t& r0, uint32_t& r1, uint32_t& r2, uint32_t& r3) {
    asm volatile("ldmatrix.sync.aligned.m8n8.x4.trans.shared.b16 {%0,%1,%2,%3}, [%4];"
                 : "=r"(r0), "=r"(r1), "=r"(r2), "=r"(r3) : "r"(addr) : "memory");
}
__device__ __forceinline__ void mma16816(float (&c)[4], uint32_t a0, uint32_t a1, uint32_t a2, uint32_t a3, uint32_t b0, uint32_t b1) {
    asm volatile("mma.sync.aligned.m16n8k16.row.col.f32.bf16.bf16.f32 {%0,%1,%2,%3}, {%4,%5,%6,%7}, {%8,%9}, {%0,%1,%2,%3};"
                 : "+f"(c[0]), "+f"(c[1]), "+f"(c[2]), "+f"(c[3])
                 : "r"(a0), "r"(a1), "r"(a2), "r"(a3), "r"(b0), "r"(b1));
}
__device__ __forceinline__ float ex2(float x) { float y; asm("ex2.approx.ftz.f32 %0, %1;" : "=f"(y) : "f"(x)); return y; }
__device__ __forceinline__ uint32_t pack_bf16(float lo, float hi) {
    uint32_t r;
    asm("cvt.rn.bf16x2.f32 %0, %1, %2;" : "=r"(r) : "f"(hi), "f"(lo));
    return r;
}
__device__ __forceinline__ float bf_lo(uint32_t v) { return __uint_as_float(v << 16); }
__device__ __forceinline__ float bf_hi(uint32_t v) { return __uint_as_float(v & 0xffff0000u); }

__device__ __forceinline__ void tma_v(uint32_t dst, const CUtensorMap* tm, uint32_t bar, int col, int row) {
    asm volatile("cp.async.bulk.tensor.2d.shared::cluster.global.mbarrier::complete_tx::bytes.L2::cache_hint [%0], [%1, {%3, %4}], [%2], %5;"
                 :: "r"(dst), "l"(tm), "r"(bar), "r"(col), "r"(row), "l"(kEvictFirst) : "memory");
}
__device__ __forceinline__ uint32_t ld_relaxed(const void* p) {
    uint32_t v; asm volatile("ld.relaxed.gpu.global.u32 %0, [%1];" : "=r"(v) : "l"(p) : "memory"); return v;
}
__device__ __forceinline__ uint4 ld_relaxed4(const void* p) {
    uint4 v; asm volatile("ld.relaxed.gpu.global.v4.u32 {%0,%1,%2,%3}, [%4];" : "=r"(v.x), "=r"(v.y), "=r"(v.z), "=r"(v.w) : "l"(p) : "memory"); return v;
}
__device__ __forceinline__ ulonglong2 ld_relaxed2x64(const void* p) {
    ulonglong2 v; asm volatile("ld.relaxed.gpu.global.v2.u64 {%0,%1}, [%2];" : "=l"(v.x), "=l"(v.y) : "l"(p) : "memory"); return v;
}
__device__ __forceinline__ void st_relaxed4(void* p, uint4 v) {
    asm volatile("st.relaxed.gpu.global.v4.u32 [%0], {%1,%2,%3,%4};" :: "l"(p), "r"(v.x), "r"(v.y), "r"(v.z), "r"(v.w) : "memory");
}
__device__ __forceinline__ void st_relaxed64(void* p, float v, uint32_t tag) {
    const unsigned long long w = ((unsigned long long)tag << 32) | __float_as_uint(v);
    asm volatile("st.relaxed.gpu.global.u64 [%0], %1;" :: "l"(p), "l"(w) : "memory");
}

__global__ void __launch_bounds__(kThreads, 1)
tree_attn_kernel(const __grid_constant__ CUtensorMap tmV, const __nv_bfloat16* __restrict__ kc,
                 const __nv_bfloat16* __restrict__ q, const __nv_bfloat16* __restrict__ k_tree,
                 const __nv_bfloat16* __restrict__ v_tree, const __nv_bfloat16* __restrict__ mask,
                 __nv_bfloat16* __restrict__ out, const int2 pace)
{
    extern __shared__ __align__(1024) unsigned char smem[];
    const uint32_t sb = (uint32_t)__cvta_generic_to_shared(smem);
    const int warp = threadIdx.x >> 5;
    const int lane = threadIdx.x & 31;
    const int rank = blockIdx.x & (kGroup - 1);
    const int hp = blockIdx.x / kGroup;
    const uint32_t barFull = sb + kOffBar;
    const uint32_t barEmpty = barFull + kStages * 8;
    const uint32_t barS = barEmpty + kStages * 8;
    const uint32_t barP = barS + kChunks * 8;
    const uint32_t barF = barP + kChunks * 8;
    const uint32_t barGo = barF + 8;

    const unsigned char* srcK = reinterpret_cast<const unsigned char*>(kc) + ((size_t)hp << 20) + (rank << 14);
    static_assert(kInit == 2 && kStageBytes == 16384 && kGroup * kStageBytes == 65536, "");
    asm volatile("{\n.reg .pred p, r;\n.reg .u64 o, a, b;\nelect.sync _|p, 0xffffffff;\n"
                 "@p mbarrier.init.shared::cta.b64 [%0], 1;\n"
                 "@p mbarrier.init.shared::cta.b64 [%0+8], 1;\n"
                 "cvt.u64.u32 o, %1;\nadd.s64 a, %2, o;\nadd.s64 b, a, 65536;\n"
                 "setp.eq.and.u32 r, %3, 0, p;\n"
                 "@r cp.async.bulk.shared::cluster.global.mbarrier::complete_tx::bytes.L2::cache_hint [%4], [a], 16384, [%6], %5;\n"
                 "@r cp.async.bulk.shared::cluster.global.mbarrier::complete_tx::bytes.L2::cache_hint [%4+16384], [b], 16384, [%6+8], %5;\n"
                 "@p mbarrier.arrive.expect_tx.shared::cta.b64 _, [%0], 16384;\n"
                 "@p mbarrier.arrive.expect_tx.shared::cta.b64 _, [%0+8], 16384;\n}"
                 :: "r"(barFull + ((threadIdx.x >> 5) << 8)), "r"((uint32_t)((hp << 20) + (rank << 14))), "l"(kc), "r"(threadIdx.x >> 5),
                    "r"(sb), "l"(kEvictFirst), "r"(barFull) : "memory");

    if (warp == 0) {
        const bool leader = elect_one();
        uint32_t t_start = 0;
        if (leader) {
            t_start = gtime32();
#pragma unroll
            for (int s = kInit; s < kStages; s++) mbar_init(barFull + s * 8, 1);
#pragma unroll
            for (int s = 0; s < kStages; s++) mbar_init(barEmpty + s * 8, kConsumerWarps);
#pragma unroll
            for (int c = 0; c < kChunks; c++) { mbar_init(barS + c * 8, kConsumerWarps); mbar_init(barP + c * 8, 3); mbar_init(barGo + c * 8, 1); }
            mbar_init(barF, 1);
        }
        __syncwarp();
        asm volatile("bar.arrive 1, %0;" :: "n"(kThreads) : "memory");
        if (leader) {
            int s = kInit % kStages; uint32_t ph = kInit / kStages ? 0 : 1;
            int sl = 0; uint32_t phl = 0;
            uint32_t due = t_start + pace.x + kInit * pace.y;
            for (int j = kInit; j < 2 * kNT; j++) {
                if (j >= kDepth) {
                    mbar_wait(barFull + sl * 8, phl);
                    if (++sl == kStages) { sl = 0; phl ^= 1; }
                }
                for (uint32_t n = 0; (int)(gtime32() - due) < 0 && n < 0x10000; n++) ;
                due += pace.y;
                mbar_wait(barEmpty + s * 8, ph);
                mbar_expect_tx(barFull + s * 8, kStageBytes);
                if (j < kNT) bulk_k(sb + s * kStageBytes, srcK + j * (kGroup * kStageBytes), barFull + s * 8);
                else tma_v(sb + s * kStageBytes, &tmV, barFull + s * 8, rank * 32, hp * kC + (j - kNT) * (kGroup * kTile));
                if (++s == kStages) { s = 0; ph ^= 1; }
                const int x = j - kDepth - 3 - kLag;
                if (x >= 0 && (x & 3) == 0 && x < 4 * kChunks) mbar_arrive(barGo + x * 2);
            }
        }
        return;
    }
    if (warp < kAuxWarps) {
        if (threadIdx.x == 96) asm volatile("prefetch.tensormap [%0];" :: "l"(&tmV) : "memory");
        asm volatile("bar.sync 1, %0;" :: "n"(kThreads) : "memory");
        const uint32_t ep = ld_relaxed(&g_epoch[blockIdx.x]) + 1;
        const uint32_t flag = ep << 31;
        if (warp == 3) {
            for (int c = 0; c < kChunks; c++) {
                mbar_wait(barGo + c * 8, 0);
                uint4 v[6];
                uint32_t pending = 0x3f;
                for (uint32_t n = 0; pending; ) {
                    if (++n > (1u << 20)) __trap();
#pragma unroll
                    for (int k = 0; k < 6; k++)
                        if (pending >> k & 1) v[k] = ld_relaxed4(&g_P[hp * kGroup + ((rank + 1 + (k >> 1)) & 3)][c * 2 + (k & 1)][lane]);
#pragma unroll
                    for (int k = 0; k < 6; k++)
                        if ((int)((v[k].x ^ flag) | (v[k].y ^ flag) | (v[k].z ^ flag) | (v[k].w ^ flag)) >= 0) pending &= ~(1u << k);
                }
#pragma unroll
                for (int k = 0; k < 6; k++)
                    *reinterpret_cast<uint4*>(smem + kOffP + ((rank + 1 + (k >> 1)) & 3) * kPRank + (k & 1) * kPPitch + c * 512 + lane * 16) =
                        make_uint4(v[k].x ^ flag, v[k].y ^ flag, v[k].z ^ flag, v[k].w ^ flag);
                __syncwarp();
                if (lane == 0) mbar_arrive(barP + c * 8);
            }
            return;
        }
        const int h = warp - 1;
        for (int c = 0; c < kChunks; c++) {
            mbar_wait(barS + c * 8, 0);
            const float4 a = *reinterpret_cast<const float4*>(smem + kOffS + h * (kSPitch * 4) + c * 1024 + lane * 32);
            const float4 b = *reinterpret_cast<const float4*>(smem + kOffS + h * (kSPitch * 4) + c * 1024 + lane * 32 + 16);
            float m = fmaxf(fmaxf(fmaxf(a.x, a.y), fmaxf(a.z, a.w)), fmaxf(fmaxf(b.x, b.y), fmaxf(b.z, b.w)));
#pragma unroll
            for (int o = 16; o > 0; o >>= 1) m = fmaxf(m, __shfl_xor_sync(~0u, m, o));
            m *= kScaleLog2e;
            const float p0 = ex2(fmaf(a.x, kScaleLog2e, -m)), p1 = ex2(fmaf(a.y, kScaleLog2e, -m));
            const float p2 = ex2(fmaf(a.z, kScaleLog2e, -m)), p3 = ex2(fmaf(a.w, kScaleLog2e, -m));
            const float p4 = ex2(fmaf(b.x, kScaleLog2e, -m)), p5 = ex2(fmaf(b.y, kScaleLog2e, -m));
            const float p6 = ex2(fmaf(b.z, kScaleLog2e, -m)), p7 = ex2(fmaf(b.w, kScaleLog2e, -m));
            uint4 pk;
            pk.x = pack_bf16(p0, p1); pk.y = pack_bf16(p2, p3); pk.z = pack_bf16(p4, p5); pk.w = pack_bf16(p6, p7);
            st_relaxed4(&g_P[blockIdx.x][c * 2 + h][lane], make_uint4(pk.x | flag, pk.y | flag, pk.z | flag, pk.w | flag));
            *reinterpret_cast<uint4*>(smem + kOffP + rank * kPRank + h * kPPitch + c * 512 + lane * 16) = pk;
            float sum = ((p0 + p1) + (p2 + p3)) + ((p4 + p5) + (p6 + p7));
#pragma unroll
            for (int o = 16; o > 0; o >>= 1) sum += __shfl_xor_sync(~0u, sum, o);
            if (lane < 2)
                st_relaxed64(reinterpret_cast<unsigned long long*>(&g_stat[blockIdx.x][c * 2 + h]) + lane, lane ? m : sum, ep);
            __syncwarp();
            if (lane == 0) mbar_arrive(barP + c * 8);
        }
        if (h != 0) return;
        const uint2 kt = __ldg(reinterpret_cast<const uint2*>(k_tree + hp * kD) + lane);
        const uint2 q0 = __ldg(reinterpret_cast<const uint2*>(q + (size_t)(hp * 2) * kD) + lane);
        const uint2 q1 = __ldg(reinterpret_cast<const uint2*>(q + (size_t)(hp * 2 + 1) * kD) + lane);
        const float mk = __bfloat162float(mask[hp / kHkv]);
        float d0 = bf_lo(kt.x) * bf_lo(q0.x) + bf_hi(kt.x) * bf_hi(q0.x) + bf_lo(kt.y) * bf_lo(q0.y) + bf_hi(kt.y) * bf_hi(q0.y);
        float d1 = bf_lo(kt.x) * bf_lo(q1.x) + bf_hi(kt.x) * bf_hi(q1.x) + bf_lo(kt.y) * bf_lo(q1.y) + bf_hi(kt.y) * bf_hi(q1.y);
#pragma unroll
        for (int o = 16; o > 0; o >>= 1) { d0 += __shfl_xor_sync(~0u, d0, o); d1 += __shfl_xor_sync(~0u, d1, o); }
        const int hh = lane & 1;
        const float xt = ((hh ? d1 : d0) * kScale + (1.0f - mk) * -1000000000.0f) * kLog2e;
        mbar_wait(barGo + (kChunks - 1) * 8, 0);
        const ulonglong2* st = &g_stat[hp * kGroup + (lane >> 3)][lane & 7];
        ulonglong2 w = ld_relaxed2x64(st);
        for (uint32_t n = 0; (uint32_t)(w.x >> 32) != ep || (uint32_t)(w.y >> 32) != ep; ) {
            if (++n > (1u << 20)) __trap();
            w = ld_relaxed2x64(st);
        }
        __syncwarp();
        const float l = __uint_as_float((uint32_t)w.x), m = __uint_as_float((uint32_t)w.y);
        float M = fmaxf(m, xt);
#pragma unroll
        for (int o = 2; o < 32; o <<= 1) M = fmaxf(M, __shfl_xor_sync(~0u, M, o));
        const float f = ex2(m - M), ft = ex2(xt - M);
        float L = f * l;
#pragma unroll
        for (int o = 2; o < 32; o <<= 1) L += __shfl_xor_sync(~0u, L, o);
        const float inv = 1.0f / (L + ft);
        float* fs = reinterpret_cast<float*>(smem + kOffF);
        fs[hh * 16 + (lane >> 1)] = f * inv;
        if (lane < 2) fs[32 + lane] = ft * inv;
        __syncwarp();
        if (lane == 0) {
            mbar_arrive(barF);
            mbar_wait(barP, 0);
            g_epoch[blockIdx.x] = ep;
        }
        return;
    }

    const int cw = warp - kAuxWarps;
    const int g = lane >> 2, t = lane & 3;
    uint4 qf[4];
#pragma unroll
    for (int i = 0; i < 4; i++) qf[i] = __ldg(reinterpret_cast<const uint4*>(q + (size_t)(hp * 2 + (g & 1)) * kD) + i * 4 + t);
    float vtree = 0.f;
    if (cw < 4) vtree = __bfloat162float(v_tree[hp * kD + rank * 32 + cw * 8 + g]);
    asm volatile("bar.sync 1, %0;" :: "n"(kThreads) : "memory");

    int s = 0; uint32_t ph = 0;
    {
        const uint32_t koff = (uint32_t)(cw * 8 + g) * 256 + t * 16 + (g & 1) * 64;
        float* Sp = reinterpret_cast<float*>(smem + kOffS) + (g & 1) * kSPitch + t * 16 + cw * 2;
        for (int j = 0; j < kNT; j++) {
            mbar_wait(barFull + s * 8, ph);
            const uint32_t base = sb + s * kStageBytes;
            const uint4 k0 = lds128(base + koff), k1 = lds128(base + (koff ^ 64));
            const uint4 k2 = lds128(base + koff + 128), k3 = lds128(base + (koff ^ 64) + 128);
            __syncwarp();
            if (lane == 0) mbar_arrive(barEmpty + s * 8);
            float c0[4] = {0.f, 0.f, 0.f, 0.f}, c1[4] = {0.f, 0.f, 0.f, 0.f};
            mma16816(c0, qf[0].x, qf[1].x, qf[0].y, qf[1].y, k0.x, k0.y);
            mma16816(c1, qf[0].z, qf[1].z, qf[0].w, qf[1].w, k0.z, k0.w);
            mma16816(c0, qf[1].x, qf[0].x, qf[1].y, qf[0].y, k1.x, k1.y);
            mma16816(c1, qf[1].z, qf[0].z, qf[1].w, qf[0].w, k1.z, k1.w);
            mma16816(c0, qf[2].x, qf[3].x, qf[2].y, qf[3].y, k2.x, k2.y);
            mma16816(c1, qf[2].z, qf[3].z, qf[2].w, qf[3].w, k2.z, k2.w);
            mma16816(c0, qf[3].x, qf[2].x, qf[3].y, qf[2].y, k3.x, k3.y);
            mma16816(c1, qf[3].z, qf[2].z, qf[3].w, qf[2].w, k3.z, k3.w);
            if (g < 2) *reinterpret_cast<float2*>(Sp + j * 64) = make_float2(c0[0] + c1[0], c0[3] + c1[3]);
            if ((j & 3) == 3) {
                __syncwarp();
                if (lane == 0) mbar_arrive(barS + (j >> 2) * 8);
            }
            if (++s == kStages) { s = 0; ph ^= 1; }
        }
    }

    if (cw >= 4) return;
    {
        const int mi = lane >> 3, i8 = lane & 7;
        const uint32_t voff = sb + (uint32_t)((mi & 1) * 64 + (mi >> 1) * 8 + i8) * 64 + ((cw ^ (i8 >> 1)) << 4);
        const uint32_t paddr = sb + kOffP + (g >> 1) * kPRank + (g & 1) * kPPitch + t * 32;
        const uint32_t faddr = sb + kOffF + t * 16;
        __nv_bfloat16* const dst = out + (size_t)(hp * 2 + (t & 1)) * kD + rank * 32 + cw * 8 + g;
        float o[2][4], val[kChunks - 1][2], r0 = 0.f, r1 = 0.f, fl0 = 0.f, fl1 = 0.f;
#pragma unroll
        for (int j = 0; j < kNT; j++) {
            const int T = kNT + j, sl = T % kStages, par = (T / kStages) & 1;
            if ((j & 3) == 0) mbar_wait(barP + (j >> 2) * 8, 0);
            const uint4 pa = lds128(paddr + j * 128), pb = lds128(paddr + j * 128 + 16);
            mbar_wait(barFull + sl * 8, par);
            uint32_t vf[4][2][4];
#pragma unroll
            for (int ks = 0; ks < 4; ks++)
#pragma unroll
                for (int rp = 0; rp < 2; rp++)
                    ldsm4t(voff + sl * kStageBytes + rp * 8192 + ks * 1024, vf[ks][rp][0], vf[ks][rp][1], vf[ks][rp][2], vf[ks][rp][3]);
            if ((j & 3) == 0) {
                if (j > 0) {
                    const float a0 = (t & 1) ? o[0][2] : o[0][0], a1 = (t & 1) ? o[0][3] : o[0][1];
                    const float b0 = (t & 1) ? o[1][2] : o[1][0], b1 = (t & 1) ? o[1][3] : o[1][1];
                    val[(j >> 2) - 1][0] = (t & 2) ? b0 : a0;
                    val[(j >> 2) - 1][1] = (t & 2) ? b1 : a1;
                }
#pragma unroll
                for (int i = 0; i < 4; i++) o[0][i] = o[1][i] = 0.f;
            }
#pragma unroll
            for (int ks = 0; ks < 4; ks++) {
                const uint32_t b0 = ks == 0 ? pa.x : ks == 1 ? pa.z : ks == 2 ? pb.x : pb.z;
                const uint32_t b1 = ks == 0 ? pa.y : ks == 1 ? pa.w : ks == 2 ? pb.y : pb.w;
#pragma unroll
                for (int rp = 0; rp < 2; rp++) mma16816(o[rp], vf[ks][rp][0], vf[ks][rp][1], vf[ks][rp][2], vf[ks][rp][3], b0, b1);
            }
            if (T + kStages < 2 * kNT) {
                __syncwarp();
                if (lane == 0) mbar_arrive2(barEmpty + sl * 8);
            }
            if (j == kFoldStep) {
                mbar_wait(barF, 0);
                const uint4 f0 = lds128(faddr), f1 = lds128(faddr + 64);
                r0 = __uint_as_float(f0.x) * val[0][0] + __uint_as_float(f0.y) * val[1][0] + __uint_as_float(f0.z) * val[2][0];
                r1 = __uint_as_float(f1.x) * val[0][1] + __uint_as_float(f1.y) * val[1][1] + __uint_as_float(f1.z) * val[2][1];
                fl0 = __uint_as_float(f0.w); fl1 = __uint_as_float(f1.w);
                const float2 ft = *reinterpret_cast<const float2*>(smem + kOffF + 128);
                if (t == 0) r0 = fmaf(ft.x, vtree, r0);
                if (t == 1) r1 = fmaf(ft.y, vtree, r1);
            }
        }
        const float a0 = (t & 1) ? o[0][2] : o[0][0], a1 = (t & 1) ? o[0][3] : o[0][1];
        const float b0 = (t & 1) ? o[1][2] : o[1][0], b1 = (t & 1) ? o[1][3] : o[1][1];
        const float x0 = fmaf(fl0, (t & 2) ? b0 : a0, r0), x1 = fmaf(fl1, (t & 2) ? b1 : a1, r1);
        const float own = (t & 1) ? x1 : x0, oth = (t & 1) ? x0 : x1;
        const float s1 = __shfl_xor_sync(~0u, oth, 1), s2 = __shfl_xor_sync(~0u, own, 2), s3 = __shfl_xor_sync(~0u, oth, 3);
        if (t < 2) *dst = __float2bfloat16((own + s1) + (s2 + s3));
    }
}

}


extern "C" void kernel_launch(void* const* d_in, const int* in_sizes, int n_in, void* d_out, int out_size) {
    const __nv_bfloat16* q  = (const __nv_bfloat16*)d_in[0];
    const __nv_bfloat16* kc = (const __nv_bfloat16*)d_in[1];
    const __nv_bfloat16* vc = (const __nv_bfloat16*)d_in[2];
    const __nv_bfloat16* kt = (const __nv_bfloat16*)d_in[3];
    const __nv_bfloat16* vt = (const __nv_bfloat16*)d_in[4];
    const __nv_bfloat16* mk = (const __nv_bfloat16*)d_in[5];
    static PFN_cuTensorMapEncodeTiled_v12000 enc = nullptr;
    static int2 pace = make_int2(0, 0);
    if (!enc) {
        cudaDriverEntryPointQueryResult qr;
        cudaGetDriverEntryPoint("cuTensorMapEncodeTiled", (void**)&enc, cudaEnableDefault, &qr);
        cudaFuncSetAttribute(tree_attn_kernel, cudaFuncAttributeMaxDynamicSharedMemorySize, kSmemBytes);
        int dev = 0, khz = 0, bits = 0;
        cudaGetDevice(&dev);
        cudaDeviceGetAttribute(&khz, cudaDevAttrMemoryClockRate, dev);
        cudaDeviceGetAttribute(&bits, cudaDevAttrGlobalMemoryBusWidth, dev);
        if (khz > 0 && bits > 0) {
            const double tau = (double)kB * kHkv * kGroup * kStageBytes / (2.0 * khz * 1e3 * (bits / 8)) * 1e9;
            if (tau < 4000.0) pace = make_int2((int)(-2.014 * tau), (int)(1.065 * tau));
        }
    }
    CUtensorMap tmV;
    {
        cuuint64_t dims[2] = {kD, (cuuint64_t)kB * kHkv * kC};
        cuuint64_t strides[1] = {256};
        cuuint32_t box[2] = {32, 256};
        cuuint32_t es[2] = {1, 1};
        enc(&tmV, CU_TENSOR_MAP_DATA_TYPE_BFLOAT16, 2, (void*)vc, dims, strides, box, es, CU_TENSOR_MAP_INTERLEAVE_NONE,
            CU_TENSOR_MAP_SWIZZLE_64B, CU_TENSOR_MAP_L2_PROMOTION_L2_128B, CU_TENSOR_MAP_FLOAT_OOB_FILL_NONE);
    }
    tree_attn_kernel<<<kB * kHkv * kGroup, kThreads, kSmemBytes, cudaStreamPerThread>>>(tmV, kc, q, kt, vt, mk, (__nv_bfloat16*)d_out, pace);
}
```
